```python
import torch

def _softmax(x, axis=-1):
    return torch.softmax(x, dim=axis)
def _gelu(x):
    return torch.nn.functional.gelu(x, approximate="tanh")
def _silu(x):
    return torch.nn.functional.silu(x)
def _sigmoid(x):
    return torch.sigmoid(x)
def _layernorm(x, axis=-1, eps=1e-5):
    m = x.mean(dim=axis, keepdim=True)
    v = x.var(dim=axis, keepdim=True, unbiased=False)
    return (x - m) / torch.sqrt(v + eps)
def _scatter_add(tgt, idx, src, axis=0):
    return tgt.clone().index_add_(axis, idx, src)
def _segment_sum(src, seg, n):
    out = torch.zeros((n,) + src.shape[1:], dtype=src.dtype)
    return out.index_add_(0, seg, src)
def _pad(x, pw):
    flat = tuple(v for pair in reversed(pw) for v in pair)
    return torch.nn.functional.pad(x, flat)

kernel_name = 'concat_heads__mha_block__softmax_full_mha__prompt'

def setup_inputs():

    _w = (lambda a: (lambda t: t.to(torch.bfloat16) if t.is_floating_point() else t)(torch.as_tensor(a)))
    def _A_setup():
        B, S, D, H = 1, 2048, 1024, 32
        return {
            "x": _w((lambda *s: torch.randn(*s, dtype=torch.bfloat16) * 0.2)(B, S, D)),
            "wqkv": _w((lambda *s: torch.randn(*s, dtype=torch.bfloat16) * 0.2)(D, 3 * D)),
            "wo": _w((lambda *s: torch.randn(*s, dtype=torch.bfloat16) * 0.05)(D, D)),
        }
    _A_in = _A_setup()

    def _B_setup():
        B, S, D = 1, 2048, 1024
        return {
            "x": _w((lambda *s: torch.randn(*s, dtype=torch.bfloat16) * 0.2)(B, S, D)),
            "wqkv": _w((lambda *s: torch.randn(*s, dtype=torch.bfloat16) * 0.2)(D, 3 * D)),
            "wo": _w((lambda *s: torch.randn(*s, dtype=torch.bfloat16) * 0.05)(D, D)),
        }
    _B_in = _B_setup()

    return {
        "A_x": _A_in["x"],
        "A_wqkv": _A_in["wqkv"],
        "A_wo": _A_in["wo"],
        "B_x": _B_in["x"],
        "B_wqkv": _B_in["wqkv"],
        "B_wo": _B_in["wo"],
    }

def reference(A_x, A_wqkv, A_wo, B_x, B_wqkv, B_wo):
    def _A_ref(x, wqkv, wo):
        B, S, D = x.shape
        H = 32
        Dh = D // H
        qkv = (lambda x, *d: x.permute(*d))((x @ wqkv).reshape(B, S, 3, H, Dh), 2, 0, 3, 1, 4)
        q, k, v = qkv[0], qkv[1], qkv[2]
        scores = torch.einsum("bhqd,bhkd->bhqk", q, k) * (Dh ** -0.5)
        p = _softmax(scores, axis=-1)
        o = torch.einsum("bhqk,bhkd->bhqd", p, v)
        return (lambda x, *d: x.permute(*d))(o, 0, 2, 1, 3).reshape(B, S, D) @ wo

    def _B_ref(x, wqkv, wo):
        B, S, D = x.shape
        H = 32; Dh = D // H
        qkv = (lambda x, *d: x.permute(*d))((x @ wqkv).reshape(B, S, 3, H, Dh), 2, 0, 3, 1, 4)
        q, k, v = qkv[0], qkv[1], qkv[2]
        scale = Dh ** -0.5
        scores = torch.einsum("bhqd,bhkd->bhqk", q, k) * scale
        p = _softmax(scores, axis=-1)
        o = torch.einsum("bhqk,bhkd->bhqd", p, v)
        return (lambda x, *d: x.permute(*d))(o, 0, 2, 1, 3).reshape(B, S, D) @ wo

    a = _A_ref(A_x, A_wqkv, A_wo)
    b = _B_ref(B_x, B_wqkv, B_wo)
    return torch.concatenate([a, b], axis=-1)
```

```cpp
#include <cuda_runtime.h>
#include <cuda.h>
#include <cuda_bf16.h>
#include <stdint.h>

namespace {

constexpr int S_LEN = 2048, D_MODEL = 1024, N_HEAD = 32, D_HEAD = 32;

__device__ __nv_bfloat16 g_qkv[2 * 3 * N_HEAD * S_LEN * D_HEAD];
__device__ __nv_bfloat16 g_o[2 * S_LEN * D_MODEL];
__device__ uint32_t g_norm[2 * 3 * N_HEAD * 1024];

__device__ uint32_t g_flag_qkv[24];
__device__ uint32_t g_flag_o[32];
__device__ uint32_t g_flag_part[128];
__device__ uint32_t g_done;
__device__ float4 g_part_o[128 * 4 * 512];
__device__ float g_part_l[128 * 256];

__device__ __forceinline__ uint32_t smem_u32(const void* p) { return (uint32_t)__cvta_generic_to_shared(p); }
__device__ __forceinline__ uint32_t tid_now() { uint32_t t; asm volatile("mov.u32 %0, %%tid.x;" : "=r"(t)); return t; }
__device__ __forceinline__ int wg_now() { return __shfl_sync(~0u, tid_now() >> 7, 0); }
__device__ __forceinline__ bool elect_one() {
    uint32_t p; asm volatile("{\n.reg .pred p;\nelect.sync _|p, 0xffffffff;\nselp.b32 %0, 1, 0, p;\n}" : "=r"(p)); return p;
}
__device__ __forceinline__ void mbar_init(uint32_t bar, uint32_t cnt) {
    asm volatile("mbarrier.init.shared::cta.b64 [%0], %1;" :: "r"(bar), "r"(cnt) : "memory");
}
__device__ __forceinline__ void mbar_expect_tx(uint32_t bar, uint32_t bytes) {
    asm volatile("mbarrier.arrive.expect_tx.shared::cta.b64 _, [%0], %1;" :: "r"(bar), "r"(bytes) : "memory");
}
__device__ __forceinline__ void mbar_arrive(uint32_t bar) {
    asm volatile("mbarrier.arrive.shared::cta.b64 _, [%0];" :: "r"(bar) : "memory");
}
__device__ __forceinline__ void mbar_arrive_cluster(uint32_t bar, uint32_t cta) {
    asm volatile("{\n.reg .b32 ra;\nmapa.shared::cluster.u32 ra, %0, %1;\n"
                 "mbarrier.arrive.shared::cluster.b64 _, [ra];\n}" :: "r"(bar), "r"(cta) : "memory");
}
__device__ __forceinline__ bool mbar_try(uint32_t bar, uint32_t parity) {
    uint32_t ok;
    asm volatile("{\n.reg .pred p;\nmbarrier.try_wait.parity.shared::cta.b64 p, [%1], %2;\nselp.b32 %0, 1, 0, p;\n}"
                 : "=r"(ok) : "r"(bar), "r"(parity) : "memory");
    return ok;
}
__device__ __forceinline__ void mbar_wait(uint32_t bar, uint32_t parity) {
    if (mbar_try(bar, parity)) return;
    uint32_t spins = 0;
    while (!mbar_try(bar, parity)) { if (++spins > (1u << 22)) break; }
}
__device__ __forceinline__ void mbar_wait_hot(uint32_t bar, uint32_t parity) {
    asm volatile("{\n.reg .pred p;\nWAIT_%=:\nmbarrier.try_wait.parity.shared::cta.b64 p, [%0], %1;\n@!p bra WAIT_%=;\n}"
                 :: "r"(bar), "r"(parity) : "memory");
}
template <int N> struct Const { static constexpr int value = N; };
__device__ __forceinline__ void mbar_wait_sleep(uint32_t bar, uint32_t parity, uint32_t ns) {
    uint32_t spins = 0;
    while (!mbar_try(bar, parity)) { __nanosleep(ns); if (++spins > (1u << 20)) break; }
}
__device__ __forceinline__ void tma_2d(uint32_t dst, const CUtensorMap* m, int c0, int c1, uint32_t bar) {
    asm volatile("cp.async.bulk.tensor.2d.shared::cluster.global.mbarrier::complete_tx::bytes [%0], [%1, {%3, %4}], [%2];"
                 :: "r"(dst), "l"(m), "r"(bar), "r"(c0), "r"(c1) : "memory");
}
__device__ __forceinline__ void tma_3d(uint32_t dst, const CUtensorMap* m, int c0, int c1, int c2, uint32_t bar) {
    asm volatile("cp.async.bulk.tensor.3d.shared::cluster.global.mbarrier::complete_tx::bytes [%0], [%1, {%3, %4, %5}], [%2];"
                 :: "r"(dst), "l"(m), "r"(bar), "r"(c0), "r"(c1), "r"(c2) : "memory");
}
__device__ __forceinline__ void tma_2d_mc(uint32_t dst, const CUtensorMap* m, int c0, int c1, uint32_t bar, uint16_t mask) {
    asm volatile("cp.async.bulk.tensor.2d.shared::cluster.global.mbarrier::complete_tx::bytes.multicast::cluster [%0], [%1, {%3, %4}], [%2], %5;"
                 :: "r"(dst), "l"(m), "r"(bar), "r"(c0), "r"(c1), "h"(mask) : "memory");
}
__device__ __forceinline__ void tma_3d_mc(uint32_t dst, const CUtensorMap* m, int c0, int c1, int c2, uint32_t bar, uint16_t mask) {
    asm volatile("cp.async.bulk.tensor.3d.shared::cluster.global.mbarrier::complete_tx::bytes.multicast::cluster [%0], [%1, {%3, %4, %5}], [%2], %6;"
                 :: "r"(dst), "l"(m), "r"(bar), "r"(c0), "r"(c1), "r"(c2), "h"(mask) : "memory");
}
__device__ __forceinline__ void prefetch_map(const CUtensorMap* m) {
    asm volatile("prefetch.tensormap [%0];" :: "l"(m) : "memory");
}
__device__ __forceinline__ void wg_fence() { asm volatile("wgmma.fence.sync.aligned;" ::: "memory"); }
__device__ __forceinline__ void wg_commit() { asm volatile("wgmma.commit_group.sync.aligned;" ::: "memory"); }
template <int N> __device__ __forceinline__ void wg_wait() { asm volatile("wgmma.wait_group.sync.aligned %0;" :: "n"(N) : "memory"); }
template <int N> __device__ __forceinline__ void reg_inc() { asm volatile("setmaxnreg.inc.sync.aligned.u32 %0;" :: "n"(N)); }
template <int N> __device__ __forceinline__ void reg_dec() { asm volatile("setmaxnreg.dec.sync.aligned.u32 %0;" :: "n"(N)); }
template <int N> __device__ __forceinline__ void fence_regs(float (&d)[N]) {
    #pragma unroll
    for (int i = 0; i < N; i++) asm volatile("" : "+f"(d[i]) :: "memory");
}
template <int N> __device__ __forceinline__ void fence_regs(uint32_t (&d)[N]) {
    #pragma unroll
    for (int i = 0; i < N; i++) asm volatile("" : "+r"(d[i]) :: "memory");
}
__host__ __device__ constexpr uint64_t mk_desc(uint32_t addr, uint32_t lbo, uint32_t sbo, uint32_t sw) {
    return (uint64_t)((addr & 0x3FFFF) >> 4) | ((uint64_t)((lbo & 0x3FFFF) >> 4) << 16) |
           ((uint64_t)((sbo & 0x3FFFF) >> 4) << 32) | ((uint64_t)sw << 62);
}
__device__ __forceinline__ uint32_t pack_bf16(float lo, float hi) {
    uint32_t r; asm("cvt.rn.bf16x2.f32 %0, %1, %2;" : "=r"(r) : "f"(hi), "f"(lo)); return r;
}
__device__ __forceinline__ float ex2(float x) { float y; asm("ex2.approx.ftz.f32 %0, %1;" : "=f"(y) : "f"(x)); return y; }
__device__ __forceinline__ uint32_t hfma2_bf16(uint32_t a, uint32_t b, uint32_t c) {
    uint32_t d; asm("fma.rn.bf16x2 %0, %1, %2, %3;" : "=r"(d) : "r"(a), "r"(b), "r"(c)); return d;
}
__device__ __forceinline__ void flag_wait(const uint32_t* f, uint32_t target, uint32_t ns) {
    uint32_t v, spins = 0;
    while (true) {
        asm volatile("ld.relaxed.gpu.global.u32 %0, [%1];" : "=r"(v) : "l"(f) : "memory");
        if (v >= target || ++spins > (1u << 20)) break;
        __nanosleep(ns);
    }
    asm volatile("ld.acquire.gpu.global.u32 %0, [%1];" : "=r"(v) : "l"(f) : "memory");
}
__device__ __forceinline__ void flag_signal(uint32_t* f) {
    asm volatile("fence.proxy.async.global;\nfence.acq_rel.gpu;\nred.relaxed.gpu.global.add.u32 [%0], 1;" :: "l"(f) : "memory");
}
__device__ __forceinline__ void bulk_load(uint32_t dst, const void* src, uint32_t bytes, uint32_t bar) {
    asm volatile("cp.async.bulk.shared::cluster.global.mbarrier::complete_tx::bytes [%0], [%1], %2, [%3];"
                 :: "r"(dst), "l"(src), "r"(bytes), "r"(bar) : "memory");
}
__device__ __forceinline__ uint32_t lds32(uint32_t a) { uint32_t v; asm volatile("ld.shared.b32 %0, [%1];" : "=r"(v) : "r"(a) : "memory"); return v; }
__device__ __forceinline__ void fence_async_smem() { asm volatile("fence.proxy.async.shared::cta;" ::: "memory"); }

__device__ __forceinline__ void wgmma_n128_ss(float (&d)[64], uint64_t da, uint64_t db, int scale_d) {
    asm volatile("{\n.reg .pred p;\nsetp.ne.b32 p, %66, 0;\n"
        "wgmma.mma_async.sync.aligned.m64n128k16.f32.bf16.bf16 {"
        "%0, %1, %2, %3, %4, %5, %6, %7, %8, %9, %10, %11, %12, %13, %14, %15, "
        "%16, %17, %18, %19, %20, %21, %22, %23, %24, %25, %26, %27, %28, %29, %30, %31, "
        "%32, %33, %34, %35, %36, %37, %38, %39, %40, %41, %42, %43, %44, %45, %46, %47, "
        "%48, %49, %50, %51, %52, %53, %54, %55, %56, %57, %58, %59, %60, %61, %62, %63"
        "}, %64, %65, p, 1, 1, 0, 1;\n}\n"
        : "+f"(d[0]), "+f"(d[1]), "+f"(d[2]), "+f"(d[3]), "+f"(d[4]), "+f"(d[5]), "+f"(d[6]), "+f"(d[7]),
          "+f"(d[8]), "+f"(d[9]), "+f"(d[10]), "+f"(d[11]), "+f"(d[12]), "+f"(d[13]), "+f"(d[14]), "+f"(d[15]),
          "+f"(d[16]), "+f"(d[17]), "+f"(d[18]), "+f"(d[19]), "+f"(d[20]), "+f"(d[21]), "+f"(d[22]), "+f"(d[23]),
          "+f"(d[24]), "+f"(d[25]), "+f"(d[26]), "+f"(d[27]), "+f"(d[28]), "+f"(d[29]), "+f"(d[30]), "+f"(d[31]),
          "+f"(d[32]), "+f"(d[33]), "+f"(d[34]), "+f"(d[35]), "+f"(d[36]), "+f"(d[37]), "+f"(d[38]), "+f"(d[39]),
          "+f"(d[40]), "+f"(d[41]), "+f"(d[42]), "+f"(d[43]), "+f"(d[44]), "+f"(d[45]), "+f"(d[46]), "+f"(d[47]),
          "+f"(d[48]), "+f"(d[49]), "+f"(d[50]), "+f"(d[51]), "+f"(d[52]), "+f"(d[53]), "+f"(d[54]), "+f"(d[55]),
          "+f"(d[56]), "+f"(d[57]), "+f"(d[58]), "+f"(d[59]), "+f"(d[60]), "+f"(d[61]), "+f"(d[62]), "+f"(d[63])
        : "l"(da), "l"(db), "r"(scale_d));
}
__device__ __forceinline__ void wgmma_n64_rs(float (&d)[32], uint32_t a0, uint32_t a1, uint32_t a2, uint32_t a3, uint64_t db, int scale_d) {
    asm volatile("{\n.reg .pred p;\nsetp.ne.b32 p, %37, 0;\n"
        "wgmma.mma_async.sync.aligned.m64n64k16.f32.bf16.bf16 {"
        "%0, %1, %2, %3, %4, %5, %6, %7, %8, %9, %10, %11, %12, %13, %14, %15, "
        "%16, %17, %18, %19, %20, %21, %22, %23, %24, %25, %26, %27, %28, %29, %30, %31"
        "}, {%32, %33, %34, %35}, %36, p, 1, 1, 0;\n}\n"
        : "+f"(d[0]), "+f"(d[1]), "+f"(d[2]), "+f"(d[3]), "+f"(d[4]), "+f"(d[5]), "+f"(d[6]), "+f"(d[7]),
          "+f"(d[8]), "+f"(d[9]), "+f"(d[10]), "+f"(d[11]), "+f"(d[12]), "+f"(d[13]), "+f"(d[14]), "+f"(d[15]),
          "+f"(d[16]), "+f"(d[17]), "+f"(d[18]), "+f"(d[19]), "+f"(d[20]), "+f"(d[21]), "+f"(d[22]), "+f"(d[23]),
          "+f"(d[24]), "+f"(d[25]), "+f"(d[26]), "+f"(d[27]), "+f"(d[28]), "+f"(d[29]), "+f"(d[30]), "+f"(d[31])
        : "r"(a0), "r"(a1), "r"(a2), "r"(a3), "l"(db), "r"(scale_d));
}
__device__ __forceinline__ void wgmma_n40_rs(float (&d)[20], uint32_t a0, uint32_t a1, uint32_t a2, uint32_t a3, uint64_t db, int scale_d) {
    asm volatile("{\n.reg .pred p;\nsetp.ne.b32 p, %25, 0;\n"
        "wgmma.mma_async.sync.aligned.m64n40k16.f32.bf16.bf16 {"
        "%0, %1, %2, %3, %4, %5, %6, %7, %8, %9, %10, %11, %12, %13, %14, %15, "
        "%16, %17, %18, %19"
        "}, {%20, %21, %22, %23}, %24, p, 1, 1, 1;\n}\n"
        : "+f"(d[0]), "+f"(d[1]), "+f"(d[2]), "+f"(d[3]), "+f"(d[4]), "+f"(d[5]), "+f"(d[6]), "+f"(d[7]),
          "+f"(d[8]), "+f"(d[9]), "+f"(d[10]), "+f"(d[11]), "+f"(d[12]), "+f"(d[13]), "+f"(d[14]), "+f"(d[15]),
          "+f"(d[16]), "+f"(d[17]), "+f"(d[18]), "+f"(d[19])
        : "r"(a0), "r"(a1), "r"(a2), "r"(a3), "l"(db), "r"(scale_d));
}

constexpr int G_STAGES = 4;
constexpr int G_A_BYTES = 128 * 64 * 2, G_B_BYTES = 64 * 256 * 2, G_STAGE_BYTES = G_A_BYTES + G_B_BYTES;
constexpr int A_STAGES = 5, A_KV = 256, A_NST = S_LEN / A_KV, A_TILES = 4;
constexpr int A_T_BYTES = A_KV * D_HEAD * 2, A_STAGE_BYTES = 2 * A_T_BYTES;
constexpr int OFF_KV = 2 * A_T_BYTES, OFF_X = G_STAGES * G_STAGE_BYTES, OFF_ONES = OFF_X + 32768, OFF_BARS = OFF_ONES + 1024;
constexpr int OFF_PART_L = OFF_BARS + 1024, SMEM_BYTES = OFF_PART_L + 1024;
constexpr uint32_t SMEM_ORG = 1024;
static_assert(OFF_KV + A_STAGES * A_STAGE_BYTES == OFF_X && SMEM_BYTES <= 232448, "smem layout");
constexpr int B_GFULL = 0, B_GEMPTY = 32, B_G1DONE = 64, B_G2READY = 96, B_GFLAG = 128, B_AFULL = 144, B_AEMPTY = 184,
              B_QFULL = 224, B_QEMPTY = 240, B_ODONE = 256, B_MODE = 288, B_MODEVAL = 320, B_PART = 336, B_READY = 344, B_S4READY = 376, B_DUMMY = 384, B_CONST = 400;

constexpr uint32_t A_SLEEP = 300, F_SLEEP = 500;

struct Stage { uint64_t dk, dv, dv_prev; uint32_t slot8, parity; };
struct Maps { CUtensorMap x[2], wqkv[2], o, wo[2], qkv; uint64_t da, db; Stage stage[A_TILES * A_NST + 1]; const __nv_bfloat16* pwo[2]; uint32_t zero; };

constexpr float EXP_MAGIC = 98304.0f + 127.0f - 77.0f / 128.0f;
constexpr float EXP_MAGIC_HI = EXP_MAGIC - 0x47C0 / 128.0f;
__device__ __forceinline__ uint32_t half_mant(uint32_t z, uint32_t mant_mask) {
    uint32_t r; asm("lop3.b32 %0, %1, %2, 0x3F003F00, 0xEA;" : "=r"(r) : "r"(z), "r"(mant_mask)); return r;
}
__device__ __forceinline__ uint32_t scaled_const(uint32_t z, uint32_t mant_mask) {
    uint32_t r; asm("lop3.b32 %0, %1, %2, 0x00030003, 0xBA;" : "=r"(r) : "r"(z), "r"(mant_mask)); return r;
}
#define SCHED_BARRIER(x) asm volatile("{.reg .pred pp; setp.eq.u32 pp, %0, 5; @pp exit;}" :: "r"(x) : "memory")
template <int POS> __device__ __forceinline__ void exp_fast(const float (&s)[32], uint32_t (&p)[16], uint32_t m0, uint32_t m1, uint32_t nv);
template <> __device__ __forceinline__ void exp_fast<0>(const float (&s)[32], uint32_t (&p)[16], uint32_t m0, uint32_t m1, uint32_t nv) {
    float e[32]; uint32_t z[16], g[16], a[16];
    e[6] = ex2(s[6]); SCHED_BARRIER(nv);
    e[9] = s[9] + EXP_MAGIC_HI; SCHED_BARRIER(nv);
    e[16] = s[16] + EXP_MAGIC; SCHED_BARRIER(nv);
    e[8] = s[8] + EXP_MAGIC; SCHED_BARRIER(nv);
    e[0] = s[0] + EXP_MAGIC; SCHED_BARRIER(nv);
    e[1] = s[1] + EXP_MAGIC_HI; SCHED_BARRIER(nv);
    e[5] = s[5] + EXP_MAGIC; SCHED_BARRIER(nv);
    e[17] = s[17] + EXP_MAGIC_HI; SCHED_BARRIER(nv);
    e[7] = ex2(s[7]); SCHED_BARRIER(nv);
    z[4] = __float_as_uint(e[9]) * 65536u + __float_as_uint(e[8]); SCHED_BARRIER(nv);
    z[8] = __float_as_uint(e[17]) * 65536u + __float_as_uint(e[16]); SCHED_BARRIER(nv);
    g[4] = half_mant(z[4], m1); SCHED_BARRIER(nv);
    e[10] = ex2(s[10]); SCHED_BARRIER(nv);
    z[0] = __float_as_uint(e[1]) * 65536u + __float_as_uint(e[0]); SCHED_BARRIER(nv);
    a[4] = scaled_const(z[4], m1); SCHED_BARRIER(nv);
    e[11] = ex2(s[11]); SCHED_BARRIER(nv);
    e[4] = s[4] + EXP_MAGIC; SCHED_BARRIER(nv);
    e[29] = s[29] + EXP_MAGIC; SCHED_BARRIER(nv);
    z[2] = __byte_perm(__float_as_uint(e[4]), __float_as_uint(e[5]), 0x5410); SCHED_BARRIER(nv);
    g[0] = half_mant(z[0], m0); SCHED_BARRIER(nv);
    e[26] = ex2(s[26]); SCHED_BARRIER(nv);
    g[2] = half_mant(z[2], m0); SCHED_BARRIER(nv);
    e[28] = s[28] + EXP_MAGIC; SCHED_BARRIER(nv);
    p[3] = pack_bf16(e[6], e[7]); SCHED_BARRIER(nv);
    g[8] = half_mant(z[8], m0); SCHED_BARRIER(nv);
    p[4] = hfma2_bf16(z[4], g[4], a[4]); SCHED_BARRIER(nv);
    a[8] = scaled_const(z[8], m0); SCHED_BARRIER(nv);
    e[27] = ex2(s[27]); SCHED_BARRIER(nv);
    e[22] = s[22] + EXP_MAGIC; SCHED_BARRIER(nv);
    a[0] = scaled_const(z[0], m0); SCHED_BARRIER(nv);
    e[15] = s[15] + EXP_MAGIC; SCHED_BARRIER(nv);
    z[14] = __byte_perm(__float_as_uint(e[28]), __float_as_uint(e[29]), 0x5410); SCHED_BARRIER(nv);
    e[14] = s[14] + EXP_MAGIC; SCHED_BARRIER(nv);
    e[12] = ex2(s[12]); SCHED_BARRIER(nv);
    p[8] = hfma2_bf16(z[8], g[8], a[8]); SCHED_BARRIER(nv);
    p[5] = pack_bf16(e[10], e[11]); SCHED_BARRIER(nv);
    e[23] = s[23] + EXP_MAGIC_HI; SCHED_BARRIER(nv);
    g[14] = half_mant(z[14], m1); SCHED_BARRIER(nv);
    e[13] = ex2(s[13]); SCHED_BARRIER(nv);
    z[7] = __byte_perm(__float_as_uint(e[14]), __float_as_uint(e[15]), 0x5410); SCHED_BARRIER(nv);
    a[2] = scaled_const(z[2], m0); SCHED_BARRIER(nv);
    e[20] = s[20] + EXP_MAGIC; SCHED_BARRIER(nv);
    e[24] = ex2(s[24]); SCHED_BARRIER(nv);
    e[21] = s[21] + EXP_MAGIC; SCHED_BARRIER(nv);
    p[13] = pack_bf16(e[26], e[27]); SCHED_BARRIER(nv);
    e[2] = s[2] + EXP_MAGIC; SCHED_BARRIER(nv);
    p[0] = hfma2_bf16(z[0], g[0], a[0]); SCHED_BARRIER(nv);
    z[11] = __float_as_uint(e[23]) * 65536u + __float_as_uint(e[22]); SCHED_BARRIER(nv);
    e[3] = s[3] + EXP_MAGIC_HI; SCHED_BARRIER(nv);
    g[7] = half_mant(z[7], m1); SCHED_BARRIER(nv);
    e[25] = ex2(s[25]); SCHED_BARRIER(nv);
    p[2] = hfma2_bf16(z[2], g[2], a[2]); SCHED_BARRIER(nv);
    a[14] = scaled_const(z[14], m0); SCHED_BARRIER(nv);
    p[6] = pack_bf16(e[12], e[13]); SCHED_BARRIER(nv);
    a[7] = scaled_const(z[7], m1); SCHED_BARRIER(nv);
    g[11] = half_mant(z[11], m0); SCHED_BARRIER(nv);
    e[18] = ex2(s[18]); SCHED_BARRIER(nv);
    z[10] = __byte_perm(__float_as_uint(e[20]), __float_as_uint(e[21]), 0x5410); SCHED_BARRIER(nv);
    e[31] = ex2(s[31]); SCHED_BARRIER(nv);
    z[1] = __float_as_uint(e[3]) * 65536u + __float_as_uint(e[2]); SCHED_BARRIER(nv);
    a[11] = scaled_const(z[11], m0); SCHED_BARRIER(nv);
    e[19] = ex2(s[19]); SCHED_BARRIER(nv);
    g[10] = half_mant(z[10], m0); SCHED_BARRIER(nv);
    a[10] = scaled_const(z[10], m0); SCHED_BARRIER(nv);
    p[14] = hfma2_bf16(z[14], g[14], a[14]); SCHED_BARRIER(nv);
    p[7] = hfma2_bf16(z[7], g[7], a[7]); SCHED_BARRIER(nv);
    g[1] = half_mant(z[1], m1); SCHED_BARRIER(nv);
    e[30] = ex2(s[30]); SCHED_BARRIER(nv);
    a[1] = scaled_const(z[1], m1); SCHED_BARRIER(nv);
    p[11] = hfma2_bf16(z[11], g[11], a[11]); SCHED_BARRIER(nv);
    p[1] = hfma2_bf16(z[1], g[1], a[1]); SCHED_BARRIER(nv);
    p[12] = pack_bf16(e[24], e[25]); SCHED_BARRIER(nv);
    p[10] = hfma2_bf16(z[10], g[10], a[10]); SCHED_BARRIER(nv);
    p[9] = pack_bf16(e[18], e[19]); SCHED_BARRIER(nv);
    p[15] = pack_bf16(e[30], e[31]); SCHED_BARRIER(nv);
}
template <> __device__ __forceinline__ void exp_fast<1>(const float (&s)[32], uint32_t (&p)[16], uint32_t m0, uint32_t m1, uint32_t nv) {
    float e[32]; uint32_t z[16], g[16], a[16];
    e[0] = s[0] + EXP_MAGIC; SCHED_BARRIER(nv);
    e[1] = s[1] + EXP_MAGIC; SCHED_BARRIER(nv);
    e[30] = ex2(s[30]); SCHED_BARRIER(nv);
    e[14] = s[14] + EXP_MAGIC; SCHED_BARRIER(nv);
    e[15] = s[15] + EXP_MAGIC_HI; SCHED_BARRIER(nv);
    e[31] = ex2(s[31]); SCHED_BARRIER(nv);
    z[0] = __byte_perm(__float_as_uint(e[0]), __float_as_uint(e[1]), 0x5410); SCHED_BARRIER(nv);
    e[10] = s[10] + EXP_MAGIC; SCHED_BARRIER(nv);
    e[11] = s[11] + EXP_MAGIC_HI; SCHED_BARRIER(nv);
    z[7] = __float_as_uint(e[15]) * 65536u + __float_as_uint(e[14]); SCHED_BARRIER(nv);
    g[0] = half_mant(z[0], m0); SCHED_BARRIER(nv);
    e[2] = ex2(s[2]); SCHED_BARRIER(nv);
    e[9] = s[9] + EXP_MAGIC; SCHED_BARRIER(nv);
    e[8] = s[8] + EXP_MAGIC; SCHED_BARRIER(nv);
    g[7] = half_mant(z[7], m0); SCHED_BARRIER(nv);
    z[5] = __float_as_uint(e[11]) * 65536u + __float_as_uint(e[10]); SCHED_BARRIER(nv);
    e[3] = ex2(s[3]); SCHED_BARRIER(nv);
    e[4] = s[4] + EXP_MAGIC; SCHED_BARRIER(nv);
    a[0] = scaled_const(z[0], m0); SCHED_BARRIER(nv);
    z[4] = __byte_perm(__float_as_uint(e[8]), __float_as_uint(e[9]), 0x5410); SCHED_BARRIER(nv);
    e[5] = s[5] + EXP_MAGIC; SCHED_BARRIER(nv);
    e[12] = s[12] + EXP_MAGIC; SCHED_BARRIER(nv);
    g[5] = half_mant(z[5], m0); SCHED_BARRIER(nv);
    e[18] = ex2(s[18]); SCHED_BARRIER(nv);
    p[15] = pack_bf16(e[30], e[31]); SCHED_BARRIER(nv);
    e[13] = s[13] + EXP_MAGIC; SCHED_BARRIER(nv);
    e[19] = ex2(s[19]); SCHED_BARRIER(nv);
    a[7] = scaled_const(z[7], m0); SCHED_BARRIER(nv);
    p[0] = hfma2_bf16(z[0], g[0], a[0]); SCHED_BARRIER(nv);
    z[2] = __byte_perm(__float_as_uint(e[4]), __float_as_uint(e[5]), 0x5410); SCHED_BARRIER(nv);
    g[4] = half_mant(z[4], m0); SCHED_BARRIER(nv);
    e[16] = s[16] + EXP_MAGIC; SCHED_BARRIER(nv);
    e[20] = ex2(s[20]); SCHED_BARRIER(nv);
    a[5] = scaled_const(z[5], m0); SCHED_BARRIER(nv);
    p[1] = pack_bf16(e[2], e[3]); SCHED_BARRIER(nv);
    p[7] = hfma2_bf16(z[7], g[7], a[7]); SCHED_BARRIER(nv);
    e[17] = s[17] + EXP_MAGIC_HI; SCHED_BARRIER(nv);
    z[6] = __byte_perm(__float_as_uint(e[12]), __float_as_uint(e[13]), 0x5410); SCHED_BARRIER(nv);
    e[21] = ex2(s[21]); SCHED_BARRIER(nv);
    g[2] = half_mant(z[2], m0); SCHED_BARRIER(nv);
    e[24] = s[24] + EXP_MAGIC; SCHED_BARRIER(nv);
    a[4] = scaled_const(z[4], m0); SCHED_BARRIER(nv);
    e[26] = ex2(s[26]); SCHED_BARRIER(nv);
    p[9] = pack_bf16(e[18], e[19]); SCHED_BARRIER(nv);
    e[25] = s[25] + EXP_MAGIC; SCHED_BARRIER(nv);
    g[6] = half_mant(z[6], m0); SCHED_BARRIER(nv);
    z[8] = __float_as_uint(e[17]) * 65536u + __float_as_uint(e[16]); SCHED_BARRIER(nv);
    p[5] = hfma2_bf16(z[5], g[5], a[5]); SCHED_BARRIER(nv);
    e[27] = ex2(s[27]); SCHED_BARRIER(nv);
    a[8] = scaled_const(z[8], m0); SCHED_BARRIER(nv);
    a[2] = scaled_const(z[2], m0); SCHED_BARRIER(nv);
    p[4] = hfma2_bf16(z[4], g[4], a[4]); SCHED_BARRIER(nv);
    e[6] = ex2(s[6]); SCHED_BARRIER(nv);
    p[10] = pack_bf16(e[20], e[21]); SCHED_BARRIER(nv);
    z[12] = __byte_perm(__float_as_uint(e[24]), __float_as_uint(e[25]), 0x5410); SCHED_BARRIER(nv);
    e[29] = s[29] + EXP_MAGIC; SCHED_BARRIER(nv);
    g[8] = half_mant(z[8], m0); SCHED_BARRIER(nv);
    e[28] = s[28] + EXP_MAGIC; SCHED_BARRIER(nv);
    e[7] = ex2(s[7]); SCHED_BARRIER(nv);
    a[6] = scaled_const(z[6], m0); SCHED_BARRIER(nv);
    p[2] = hfma2_bf16(z[2], g[2], a[2]); SCHED_BARRIER(nv);
    z[14] = __byte_perm(__float_as_uint(e[28]), __float_as_uint(e[29]), 0x5410); SCHED_BARRIER(nv);
    g[12] = half_mant(z[12], m0); SCHED_BARRIER(nv);
    p[6] = hfma2_bf16(z[6], g[6], a[6]); SCHED_BARRIER(nv);
    p[13] = pack_bf16(e[26], e[27]); SCHED_BARRIER(nv);
    e[22] = ex2(s[22]); SCHED_BARRIER(nv);
    a[12] = scaled_const(z[12], m0); SCHED_BARRIER(nv);
    a[14] = scaled_const(z[14], m0); SCHED_BARRIER(nv);
    g[14] = half_mant(z[14], m0); SCHED_BARRIER(nv);
    p[8] = hfma2_bf16(z[8], g[8], a[8]); SCHED_BARRIER(nv);
    p[3] = pack_bf16(e[6], e[7]); SCHED_BARRIER(nv);
    e[23] = ex2(s[23]); SCHED_BARRIER(nv);
    p[12] = hfma2_bf16(z[12], g[12], a[12]); SCHED_BARRIER(nv);
    p[14] = hfma2_bf16(z[14], g[14], a[14]); SCHED_BARRIER(nv);
    p[11] = pack_bf16(e[22], e[23]); SCHED_BARRIER(nv);
}
template <> __device__ __forceinline__ void exp_fast<2>(const float (&s)[32], uint32_t (&p)[16], uint32_t m0, uint32_t m1, uint32_t nv) {
    float e[32]; uint32_t z[16], g[16], a[16];
    e[0] = s[0] + EXP_MAGIC; SCHED_BARRIER(nv);
    e[1] = s[1] + EXP_MAGIC; SCHED_BARRIER(nv);
    e[30] = ex2(s[30]); SCHED_BARRIER(nv);
    e[14] = s[14] + EXP_MAGIC; SCHED_BARRIER(nv);
    e[15] = s[15] + EXP_MAGIC_HI; SCHED_BARRIER(nv);
    e[31] = ex2(s[31]); SCHED_BARRIER(nv);
    z[0] = __byte_perm(__float_as_uint(e[0]), __float_as_uint(e[1]), 0x5410); SCHED_BARRIER(nv);
    e[10] = s[10] + EXP_MAGIC; SCHED_BARRIER(nv);
    e[11] = s[11] + EXP_MAGIC_HI; SCHED_BARRIER(nv);
    z[7] = __float_as_uint(e[15]) * 65536u + __float_as_uint(e[14]); SCHED_BARRIER(nv);
    g[0] = half_mant(z[0], m0); SCHED_BARRIER(nv);
    e[2] = ex2(s[2]); SCHED_BARRIER(nv);
    e[9] = s[9] + EXP_MAGIC; SCHED_BARRIER(nv);
    e[8] = s[8] + EXP_MAGIC; SCHED_BARRIER(nv);
    g[7] = half_mant(z[7], m0); SCHED_BARRIER(nv);
    z[5] = __float_as_uint(e[11]) * 65536u + __float_as_uint(e[10]); SCHED_BARRIER(nv);
    e[3] = ex2(s[3]); SCHED_BARRIER(nv);
    e[4] = s[4] + EXP_MAGIC; SCHED_BARRIER(nv);
    a[0] = scaled_const(z[0], m0); SCHED_BARRIER(nv);
    z[4] = __byte_perm(__float_as_uint(e[8]), __float_as_uint(e[9]), 0x5410); SCHED_BARRIER(nv);
    e[5] = s[5] + EXP_MAGIC; SCHED_BARRIER(nv);
    e[12] = s[12] + EXP_MAGIC; SCHED_BARRIER(nv);
    g[5] = half_mant(z[5], m0); SCHED_BARRIER(nv);
    e[18] = ex2(s[18]); SCHED_BARRIER(nv);
    p[15] = pack_bf16(e[30], e[31]); SCHED_BARRIER(nv);
    e[13] = s[13] + EXP_MAGIC; SCHED_BARRIER(nv);
    e[19] = ex2(s[19]); SCHED_BARRIER(nv);
    a[7] = scaled_const(z[7], m0); SCHED_BARRIER(nv);
    p[0] = hfma2_bf16(z[0], g[0], a[0]); SCHED_BARRIER(nv);
    z[2] = __byte_perm(__float_as_uint(e[4]), __float_as_uint(e[5]), 0x5410); SCHED_BARRIER(nv);
    g[4] = half_mant(z[4], m0); SCHED_BARRIER(nv);
    e[16] = s[16] + EXP_MAGIC; SCHED_BARRIER(nv);
    e[20] = ex2(s[20]); SCHED_BARRIER(nv);
    a[5] = scaled_const(z[5], m0); SCHED_BARRIER(nv);
    p[1] = pack_bf16(e[2], e[3]); SCHED_BARRIER(nv);
    p[7] = hfma2_bf16(z[7], g[7], a[7]); SCHED_BARRIER(nv);
    e[17] = s[17] + EXP_MAGIC_HI; SCHED_BARRIER(nv);
    z[6] = __byte_perm(__float_as_uint(e[12]), __float_as_uint(e[13]), 0x5410); SCHED_BARRIER(nv);
    e[21] = ex2(s[21]); SCHED_BARRIER(nv);
    g[2] = half_mant(z[2], m0); SCHED_BARRIER(nv);
    e[24] = s[24] + EXP_MAGIC; SCHED_BARRIER(nv);
    a[4] = scaled_const(z[4], m0); SCHED_BARRIER(nv);
    e[26] = ex2(s[26]); SCHED_BARRIER(nv);
    p[9] = pack_bf16(e[18], e[19]); SCHED_BARRIER(nv);
    e[25] = s[25] + EXP_MAGIC; SCHED_BARRIER(nv);
    g[6] = half_mant(z[6], m0); SCHED_BARRIER(nv);
    z[8] = __float_as_uint(e[17]) * 65536u + __float_as_uint(e[16]); SCHED_BARRIER(nv);
    p[5] = hfma2_bf16(z[5], g[5], a[5]); SCHED_BARRIER(nv);
    e[27] = ex2(s[27]); SCHED_BARRIER(nv);
    a[2] = scaled_const(z[2], m0); SCHED_BARRIER(nv);
    a[8] = scaled_const(z[8], m0); SCHED_BARRIER(nv);
    p[4] = hfma2_bf16(z[4], g[4], a[4]); SCHED_BARRIER(nv);
    e[6] = ex2(s[6]); SCHED_BARRIER(nv);
    p[10] = pack_bf16(e[20], e[21]); SCHED_BARRIER(nv);
    z[12] = __byte_perm(__float_as_uint(e[24]), __float_as_uint(e[25]), 0x5410); SCHED_BARRIER(nv);
    e[29] = s[29] + EXP_MAGIC; SCHED_BARRIER(nv);
    g[8] = half_mant(z[8], m0); SCHED_BARRIER(nv);
    e[28] = s[28] + EXP_MAGIC; SCHED_BARRIER(nv);
    e[7] = ex2(s[7]); SCHED_BARRIER(nv);
    a[6] = scaled_const(z[6], m0); SCHED_BARRIER(nv);
    p[2] = hfma2_bf16(z[2], g[2], a[2]); SCHED_BARRIER(nv);
    z[14] = __byte_perm(__float_as_uint(e[28]), __float_as_uint(e[29]), 0x5410); SCHED_BARRIER(nv);
    g[12] = half_mant(z[12], m0); SCHED_BARRIER(nv);
    p[6] = hfma2_bf16(z[6], g[6], a[6]); SCHED_BARRIER(nv);
    p[13] = pack_bf16(e[26], e[27]); SCHED_BARRIER(nv);
    e[22] = ex2(s[22]); SCHED_BARRIER(nv);
    a[12] = scaled_const(z[12], m0); SCHED_BARRIER(nv);
    a[14] = scaled_const(z[14], m0); SCHED_BARRIER(nv);
    g[14] = half_mant(z[14], m0); SCHED_BARRIER(nv);
    p[8] = hfma2_bf16(z[8], g[8], a[8]); SCHED_BARRIER(nv);
    p[3] = pack_bf16(e[6], e[7]); SCHED_BARRIER(nv);
    e[23] = ex2(s[23]); SCHED_BARRIER(nv);
    p[12] = hfma2_bf16(z[12], g[12], a[12]); SCHED_BARRIER(nv);
    p[14] = hfma2_bf16(z[14], g[14], a[14]); SCHED_BARRIER(nv);
    p[11] = pack_bf16(e[22], e[23]); SCHED_BARRIER(nv);
}
template <> __device__ __forceinline__ void exp_fast<3>(const float (&s)[32], uint32_t (&p)[16], uint32_t m0, uint32_t m1, uint32_t nv) {
    float e[32]; uint32_t z[16], g[16], a[16];
    e[8] = s[8] + EXP_MAGIC; SCHED_BARRIER(nv);
    e[9] = s[9] + EXP_MAGIC; SCHED_BARRIER(nv);
    e[30] = ex2(s[30]); SCHED_BARRIER(nv);
    e[14] = s[14] + EXP_MAGIC; SCHED_BARRIER(nv);
    e[15] = s[15] + EXP_MAGIC_HI; SCHED_BARRIER(nv);
    e[31] = ex2(s[31]); SCHED_BARRIER(nv);
    z[4] = __byte_perm(__float_as_uint(e[8]), __float_as_uint(e[9]), 0x5410); SCHED_BARRIER(nv);
    e[10] = s[10] + EXP_MAGIC; SCHED_BARRIER(nv);
    e[11] = s[11] + EXP_MAGIC_HI; SCHED_BARRIER(nv);
    z[7] = __float_as_uint(e[15]) * 65536u + __float_as_uint(e[14]); SCHED_BARRIER(nv);
    g[4] = half_mant(z[4], m0); SCHED_BARRIER(nv);
    e[2] = ex2(s[2]); SCHED_BARRIER(nv);
    e[1] = s[1] + EXP_MAGIC; SCHED_BARRIER(nv);
    e[0] = s[0] + EXP_MAGIC; SCHED_BARRIER(nv);
    g[7] = half_mant(z[7], m0); SCHED_BARRIER(nv);
    z[5] = __float_as_uint(e[11]) * 65536u + __float_as_uint(e[10]); SCHED_BARRIER(nv);
    e[3] = ex2(s[3]); SCHED_BARRIER(nv);
    e[4] = s[4] + EXP_MAGIC; SCHED_BARRIER(nv);
    a[4] = scaled_const(z[4], m0); SCHED_BARRIER(nv);
    z[0] = __byte_perm(__float_as_uint(e[0]), __float_as_uint(e[1]), 0x5410); SCHED_BARRIER(nv);
    e[5] = s[5] + EXP_MAGIC; SCHED_BARRIER(nv);
    e[12] = s[12] + EXP_MAGIC; SCHED_BARRIER(nv);
    g[5] = half_mant(z[5], m0); SCHED_BARRIER(nv);
    e[18] = ex2(s[18]); SCHED_BARRIER(nv);
    p[15] = pack_bf16(e[30], e[31]); SCHED_BARRIER(nv);
    e[13] = s[13] + EXP_MAGIC; SCHED_BARRIER(nv);
    e[19] = ex2(s[19]); SCHED_BARRIER(nv);
    a[7] = scaled_const(z[7], m0); SCHED_BARRIER(nv);
    p[4] = hfma2_bf16(z[4], g[4], a[4]); SCHED_BARRIER(nv);
    z[2] = __byte_perm(__float_as_uint(e[4]), __float_as_uint(e[5]), 0x5410); SCHED_BARRIER(nv);
    g[0] = half_mant(z[0], m0); SCHED_BARRIER(nv);
    e[16] = s[16] + EXP_MAGIC; SCHED_BARRIER(nv);
    e[20] = ex2(s[20]); SCHED_BARRIER(nv);
    a[5] = scaled_const(z[5], m0); SCHED_BARRIER(nv);
    p[1] = pack_bf16(e[2], e[3]); SCHED_BARRIER(nv);
    p[7] = hfma2_bf16(z[7], g[7], a[7]); SCHED_BARRIER(nv);
    e[17] = s[17] + EXP_MAGIC_HI; SCHED_BARRIER(nv);
    z[6] = __byte_perm(__float_as_uint(e[12]), __float_as_uint(e[13]), 0x5410); SCHED_BARRIER(nv);
    e[21] = ex2(s[21]); SCHED_BARRIER(nv);
    g[2] = half_mant(z[2], m0); SCHED_BARRIER(nv);
    e[24] = s[24] + EXP_MAGIC; SCHED_BARRIER(nv);
    a[0] = scaled_const(z[0], m0); SCHED_BARRIER(nv);
    p[5] = hfma2_bf16(z[5], g[5], a[5]); SCHED_BARRIER(nv);
    e[26] = ex2(s[26]); SCHED_BARRIER(nv);
    p[9] = pack_bf16(e[18], e[19]); SCHED_BARRIER(nv);
    e[25] = s[25] + EXP_MAGIC; SCHED_BARRIER(nv);
    g[6] = half_mant(z[6], m0); SCHED_BARRIER(nv);
    z[8] = __float_as_uint(e[17]) * 65536u + __float_as_uint(e[16]); SCHED_BARRIER(nv);
    e[27] = ex2(s[27]); SCHED_BARRIER(nv);
    a[8] = scaled_const(z[8], m0); SCHED_BARRIER(nv);
    a[2] = scaled_const(z[2], m0); SCHED_BARRIER(nv);
    p[0] = hfma2_bf16(z[0], g[0], a[0]); SCHED_BARRIER(nv);
    e[6] = ex2(s[6]); SCHED_BARRIER(nv);
    p[10] = pack_bf16(e[20], e[21]); SCHED_BARRIER(nv);
    z[12] = __byte_perm(__float_as_uint(e[24]), __float_as_uint(e[25]), 0x5410); SCHED_BARRIER(nv);
    e[29] = s[29] + EXP_MAGIC; SCHED_BARRIER(nv);
    g[8] = half_mant(z[8], m0); SCHED_BARRIER(nv);
    e[28] = s[28] + EXP_MAGIC; SCHED_BARRIER(nv);
    e[7] = ex2(s[7]); SCHED_BARRIER(nv);
    a[6] = scaled_const(z[6], m0); SCHED_BARRIER(nv);
    p[2] = hfma2_bf16(z[2], g[2], a[2]); SCHED_BARRIER(nv);
    z[14] = __byte_perm(__float_as_uint(e[28]), __float_as_uint(e[29]), 0x5410); SCHED_BARRIER(nv);
    g[12] = half_mant(z[12], m0); SCHED_BARRIER(nv);
    p[6] = hfma2_bf16(z[6], g[6], a[6]); SCHED_BARRIER(nv);
    p[13] = pack_bf16(e[26], e[27]); SCHED_BARRIER(nv);
    e[22] = ex2(s[22]); SCHED_BARRIER(nv);
    a[12] = scaled_const(z[12], m0); SCHED_BARRIER(nv);
    a[14] = scaled_const(z[14], m0); SCHED_BARRIER(nv);
    g[14] = half_mant(z[14], m0); SCHED_BARRIER(nv);
    p[8] = hfma2_bf16(z[8], g[8], a[8]); SCHED_BARRIER(nv);
    p[3] = pack_bf16(e[6], e[7]); SCHED_BARRIER(nv);
    e[23] = ex2(s[23]); SCHED_BARRIER(nv);
    p[12] = hfma2_bf16(z[12], g[12], a[12]); SCHED_BARRIER(nv);
    p[14] = hfma2_bf16(z[14], g[14], a[14]); SCHED_BARRIER(nv);
    p[11] = pack_bf16(e[22], e[23]); SCHED_BARRIER(nv);
}
__device__ __forceinline__ void mma_qk(float (&s)[32], const uint32_t (&q)[8], uint64_t dk) {
    wgmma_n64_rs(s, q[0], q[1], q[2], q[3], dk, 0);
    wgmma_n64_rs(s, q[4], q[5], q[6], q[7], dk + 2, 1);
}
constexpr uint64_t V_STEP = (uint64_t)1 - ((uint64_t)1 << 16);
__device__ __forceinline__ void mma_pv(float (&o)[20], const uint32_t (&p)[16], uint64_t dv, int keep) {
    #pragma unroll
    for (int k = 0; k < 4; k++)
        wgmma_n40_rs(o, p[4 * k], p[4 * k + 1], p[4 * k + 2], p[4 * k + 3], dv + (uint64_t)(k * 64) * V_STEP, k > 0 ? 1 : keep);
}
__device__ __forceinline__ void load_q(uint32_t (&q)[8], uint32_t addr) {
    #pragma unroll
    for (int kk = 0; kk < 2; kk++)
        asm volatile("ldmatrix.sync.aligned.m8n8.x4.shared.b16 {%0, %1, %2, %3}, [%4];"
                     : "=r"(q[4 * kk]), "=r"(q[4 * kk + 1]), "=r"(q[4 * kk + 2]), "=r"(q[4 * kk + 3]) : "r"(addr ^ (32 * kk)) : "memory");
}
__device__ __forceinline__ void inv_sums(const float (&o)[20], float& i0, float& i1) {
    asm("rcp.approx.ftz.f32 %0, %1;" : "=f"(i0) : "f"(o[16]));
    asm("rcp.approx.ftz.f32 %0, %1;" : "=f"(i1) : "f"(o[18]));
    i0 = __shfl_sync(~0u, i0, 0, 4); i1 = __shfl_sync(~0u, i1, 0, 4);
}
__device__ __forceinline__ void store_o(const float (&o)[20], float i0, float i1, __nv_bfloat16* dst) {
    *reinterpret_cast<uint4*>(dst) = make_uint4(pack_bf16(o[0] * i0, o[1] * i0), pack_bf16(o[4] * i0, o[5] * i0),
                                                pack_bf16(o[8] * i0, o[9] * i0), pack_bf16(o[12] * i0, o[13] * i0));
    *reinterpret_cast<uint4*>(dst + 8 * D_MODEL) = make_uint4(pack_bf16(o[2] * i1, o[3] * i1), pack_bf16(o[6] * i1, o[7] * i1),
                                                              pack_bf16(o[10] * i1, o[11] * i1), pack_bf16(o[14] * i1, o[15] * i1));
}


struct Turn {
    uint32_t mine, next;
    __device__ __forceinline__ explicit Turn(uint32_t tid) : mine(2 + (tid >> 7)), next(2 + (((tid >> 7) + 1) & 3)) {}
    __device__ __forceinline__ void take() const { asm volatile("bar.sync %0, 256;" :: "r"(mine) : "memory"); }
    __device__ __forceinline__ void pass() const { asm volatile("bar.arrive %0, 256;" :: "r"(next) : "memory"); }
};

__device__ __forceinline__ int g1_tile(int r, int cluster) {
    const int s = (r * 64 + cluster) >> 3, half = s >= 6;
    return s >= 12 ? s : ((s - 6 * half) >> 1) * 4 + half * 2 + (s & 1);
}

template <int ROT, bool LAST, typename Mid>
__device__ __forceinline__ void gemm_tile(float (&acc)[64], uint32_t bars, const Maps& maps, int wg, uint32_t tid, Mid mid) {
    const Turn turn(tid);
    const bool elect = (tid & 127) == 0;
    uint32_t empty_peer;
    asm("mapa.shared::cluster.u32 %0, %1, %2;" : "=r"(empty_peer) : "r"(bars + B_GEMPTY), "r"((blockIdx.x & 1) ^ 1));
    uint64_t da0 = maps.da + (uint32_t)((wg & 1) * (8192 >> 4));
    uint64_t db0 = maps.db + (uint32_t)((wg >> 1) * (16384 >> 4));
    #pragma unroll 1
    for (int k4 = 0; k4 < 4; k4++) {
        da0 += maps.zero; db0 += maps.zero;
        #pragma unroll
        for (int j = 0; j < 4; j++) {
            const int s = (j + ROT) & 3;
            mbar_wait_hot(bars + B_GFULL + 8 * s, k4 & 1);
            const uint64_t da = da0 + (uint32_t)(s * (G_STAGE_BYTES >> 4)), db = db0 + (uint32_t)(s * (G_STAGE_BYTES >> 4));
            const bool joined = LAST && k4 == 3;
            if (!(j == 3 && joined)) turn.take();
            wg_fence();
            #pragma unroll
            for (int k = 0; k < 4; k++) wgmma_n128_ss(acc, da + k * 2, db + k * 128, (j | k) != 0 ? 1 : k4 != 0);
            wg_commit();
            if (j == 2 && joined) continue;
            turn.pass();
            wg_wait<0>();
            if (elect && !joined) {
                mbar_arrive(bars + B_GEMPTY + 8 * s);
                asm volatile("mbarrier.arrive.shared::cluster.b64 _, [%0];" :: "r"(empty_peer + 8 * s) : "memory");
            }
            mid(k4, j);
        }
    }
    fence_regs(acc);
}

__global__ void __cluster_dims__(2, 1, 1) __launch_bounds__(640, 1)
mha2_kernel(const __grid_constant__ Maps maps, __nv_bfloat16* out) {
    extern __shared__ __align__(1024) uint8_t smem_raw[];
    const uint32_t base = smem_u32(smem_raw);
    const uint32_t bars = base + OFF_BARS;
    const uint32_t rank = blockIdx.x & 1;
    const int cluster = blockIdx.x >> 1;
    const int mt = (cluster & 7) * 2 + rank;
    const int blk3 = cluster >> 5, nt3 = (cluster >> 3) & 3;
    const bool spare = blockIdx.x >= 128;
    const int tl_give = gridDim.x > 128 ? (blockIdx.x >> 3) & 3 : 4;
    auto head_of = [&](int g) { return spare ? g * 17 + (blockIdx.x - 128) * 4 : g * 16 + (blockIdx.x >> 3); };

    const int wid = __shfl_sync(~0u, threadIdx.x >> 5, 0);
    if (wid == 16 && elect_one()) {
        mbar_init(bars + B_GFULL, 1);
        if (!spare) {
            asm volatile("fence.mbarrier_init.release.cluster;" ::: "memory");
            const int c2 = g1_tile(0, cluster) * 4;
            mbar_expect_tx(bars + B_GFULL, G_STAGE_BYTES);
            tma_2d(base, &maps.x[0], 0, mt * 128, bars + B_GFULL);
            tma_3d(base + G_A_BYTES, &maps.wqkv[0], 0, 0, c2, bars + B_GFULL);
            tma_3d(base + G_A_BYTES + G_B_BYTES / 2, &maps.wqkv[0], 0, 0, c2 + 2, bars + B_GFULL);
        }
        if ((base & 0x3FFFF) != SMEM_ORG) __trap();
        for (int s = 0; s < G_STAGES; s++) {
            if (s) mbar_init(bars + B_GFULL + 8 * s, 1);
            mbar_init(bars + B_GEMPTY + 8 * s, 8); mbar_init(bars + B_G2READY + 8 * s, 2);
        }
        for (int s = 0; s < 4; s++) mbar_init(bars + B_G1DONE + 8 * s, 16);
        for (int s = 0; s < A_STAGES; s++) { mbar_init(bars + B_AFULL + 8 * s, 1); mbar_init(bars + B_AEMPTY + 8 * s, 8); }
        for (int s = 0; s < 2; s++) {
            mbar_init(bars + B_QFULL + 8 * s, 1); mbar_init(bars + B_QEMPTY + 8 * s, 16); mbar_init(bars + B_GFLAG + 8 * s, 1);
        }
        for (int s = 0; s < A_TILES; s++) { mbar_init(bars + B_ODONE + 8 * s, 16); mbar_init(bars + B_MODE + 8 * s, 1); mbar_init(bars + B_READY + 8 * s, 1); }
        mbar_init(bars + B_PART, 1); mbar_init(bars + B_S4READY, 2); mbar_init(bars + B_DUMMY, 1);
        if (spare) for (int s = 0; s < 32; s++) mbar_init(base + OFF_X + 8 * s, 16);
        asm volatile("fence.mbarrier_init.release.cluster;" ::: "memory");
    }
    __syncwarp();
    asm volatile("barrier.cluster.arrive.relaxed.aligned;" ::: "memory");
    if (wid == 16 && !spare && elect_one()) {
        for (int k = 1; k < G_STAGES; k++) mbar_expect_tx(bars + B_GFULL + 8 * k, G_STAGE_BYTES);
        tma_2d(base + G_STAGE_BYTES, &maps.x[0], 64, mt * 128, bars + B_GFULL + 8);
    }
    if (threadIdx.x < 256) {
        if (threadIdx.x < 4) asm volatile("st.shared.b32 [%0], %1;" :: "r"(bars + B_CONST + 4 * threadIdx.x), "r"(0x007F007Fu) : "memory");
        asm volatile("st.shared.b32 [%0], %1;" :: "r"(base + OFF_ONES + 4 * threadIdx.x),
                     "r"((threadIdx.x & 3) == 0 ? 0x00003F80u : 0u) : "memory");
        fence_async_smem();
    }
    __syncwarp();
    asm volatile("barrier.cluster.wait.aligned;" ::: "memory");
    if (wid == 16) {
        if (!spare && elect_one()) {
            const int c2 = g1_tile(0, cluster) * 4 + rank * 2;
            tma_3d_mc(base + G_STAGE_BYTES + G_A_BYTES + rank * (G_B_BYTES / 2), &maps.wqkv[0], 0, 64, c2, bars + B_GFULL + 8, 3);
        }
        __syncwarp();
    }

    if (wid >= 16) {
        reg_dec<32>();
        const int lane = threadIdx.x & 31;
        const bool leader = elect_one();
        if (wid == 16 && leader && spare) {
            for (int n = 0; n < 32; n++) {
                const int g = n >> 3, head = head_of(g), rq = ((head >> 5) * 96 + (head & 31)) * S_LEN;
                if ((n & 7) == 0) {
                    mbar_wait_sleep(bars + B_READY + 8 * g, 0, 100);
                    const uint32_t dst = base + OFF_KV + g * A_STAGE_BYTES, full = bars + B_AFULL + 8 * g;
                    mbar_expect_tx(full, A_STAGE_BYTES);
                    tma_2d(dst, &maps.qkv, 0, rq + 33 * S_LEN - A_KV, full);
                    tma_2d(dst + A_T_BYTES, &maps.qkv, 0, rq + 65 * S_LEN - A_KV, full);
                }
                mbar_wait_sleep(bars + B_QEMPTY + 8 * (n & 1), ((n >> 1) & 1) ^ 1, 100);
                mbar_expect_tx(bars + B_QFULL + 8 * (n & 1), A_T_BYTES);
                tma_2d(base + (n & 1) * A_T_BYTES, &maps.qkv, 0, rq + (n & 7) * 256, bars + B_QFULL + 8 * (n & 1));
            }
        } else if (wid == 16 && leader) {
            prefetch_map(&maps.x[1]); prefetch_map(&maps.wqkv[1]); prefetch_map(&maps.qkv);
            prefetch_map(&maps.o); prefetch_map(&maps.wo[blk3]);
            mbar_wait(bars + B_GFULL, 0);
            for (int r = 0; r < 3; r++) {
                const int ct = g1_tile(r, cluster), blk = ct >= 12, c2 = (ct - 12 * blk) * 4 + rank * 2;
                const CUtensorMap* ma = &maps.x[blk];
                const CUtensorMap* mb = &maps.wqkv[blk];
                for (int kt = r == 0 ? 2 : 0; kt < 16; kt++) {
                    const int s = kt & 3;
                    const uint32_t st = base + s * G_STAGE_BYTES, full = bars + B_GFULL + 8 * s;
                    if (r > 0 || kt >= G_STAGES) {
                        mbar_wait(bars + B_GEMPTY + 8 * s, ((kt >> 2) - 1) & 1);
                        mbar_expect_tx(full, G_STAGE_BYTES);
                    }
                    tma_2d(st, ma, kt * 64, mt * 128, full);
                    tma_3d_mc(st + G_A_BYTES + rank * (G_B_BYTES / 2), mb, 0, kt * 64, c2, full, 3);
                }
            }
            int c = 0;
            for (int tl = 0; tl < A_TILES; tl++) {
                const int head = head_of(tl), rq = ((head >> 5) * 96 + (head & 31)) * S_LEN;
                mbar_wait_sleep(bars + B_MODE + 8 * tl, 0, 100);
                if (tl == 0) mbar_wait(bars + B_GEMPTY, 1);
                else mbar_wait_sleep(bars + B_QEMPTY + 8 * (tl & 1), ((tl >> 1) & 1) ^ 1, A_SLEEP);
                mbar_expect_tx(bars + B_QFULL + 8 * (tl & 1), A_T_BYTES);
                tma_2d(base + (tl & 1) * A_T_BYTES, &maps.qkv, 0, rq + (blockIdx.x & 7) * 256, bars + B_QFULL + 8 * (tl & 1));
                for (int st = 0; st < A_NST; st++, c++) {
                    const int s = c % A_STAGES;
                    if (c == A_STAGES - 1) {
                        mbar_wait_sleep(bars + B_G1DONE + 24, 0, 100);
                        mbar_arrive_cluster(bars + B_S4READY, 0); mbar_arrive_cluster(bars + B_S4READY, 1);
                        mbar_wait_sleep(bars + B_S4READY, 0, 50);
                    }
                    else if (c < A_STAGES) mbar_wait(bars + B_GEMPTY + 8 * ((2 * c + 3) / 3), 1);
                    else mbar_wait_sleep(bars + B_AEMPTY + 8 * s, ((c / A_STAGES) - 1) & 1, A_SLEEP);
                    const uint32_t dst = base + OFF_KV + s * A_STAGE_BYTES, full = bars + B_AFULL + 8 * s;
                    if (st == A_NST - 1 && tl == tl_give && lds32(bars + B_MODEVAL + 4 * tl)) {
                        mbar_arrive(full);
                        continue;
                    }
                    mbar_expect_tx(full, A_STAGE_BYTES);
                    tma_2d_mc(dst + rank * A_T_BYTES, &maps.qkv, 0, rq + (32 + 32 * rank) * S_LEN + st * A_KV, full, 3);
                }
            }
            auto wait_vacated = [&](int s) { mbar_wait_sleep(bars + B_AEMPTY + 8 * s, ((A_TILES * A_NST - 1 - s) / A_STAGES) & 1, 50); };
            for (int kt = 0; kt < 16; kt++) {
                const int s = (kt + 2) & 3;
                const uint32_t st = base + s * G_STAGE_BYTES, full = bars + B_GFULL + 8 * s;
                if ((kt & 7) == 0) mbar_wait_sleep(bars + B_GFLAG + (kt & 8), 0, 50);
                if (kt < G_STAGES) {
                    if (kt == 0) wait_vacated(2);
                    wait_vacated((kt + 3) % A_STAGES);
                    mbar_arrive_cluster(bars + B_G2READY + 8 * kt, 0); mbar_arrive_cluster(bars + B_G2READY + 8 * kt, 1);
                } else {
                    mbar_wait(bars + B_GEMPTY + 8 * s, ((kt >> 2) - 1) & 1);
                }
                mbar_expect_tx(full, G_STAGE_BYTES);
                tma_2d(st, &maps.o, kt * 64, blk3 * S_LEN + mt * 128, full);
                if (kt < G_STAGES) mbar_wait_sleep(bars + B_G2READY + 8 * kt, 0, 20);
                tma_3d_mc(st + G_A_BYTES + rank * (G_B_BYTES / 2), &maps.wo[blk3], 0, kt * 64, nt3 * 4 + rank * 2, full, 3);
            }
        } else if (wid == 17 && leader && spare) {
            for (int n = 0; n < 32; n++) {
                mbar_wait_sleep(bars + B_MODE + 8 * (n >> 3), 0, 200);
                if (!lds32(bars + B_MODEVAL + 4 * (n >> 3))) continue;
                mbar_wait_sleep(base + OFF_X + 8 * n, 0, 100);
                flag_signal(&g_flag_part[(blockIdx.x - 128) * 32 + n]);
            }
        } else if (wid == 19 && leader) {
            if (!spare && tl_give < A_TILES) {
                mbar_wait_sleep(bars + B_MODE + 8 * tl_give, 0, 500);
                if (lds32(bars + B_MODEVAL + 4 * tl_give)) {
                    mbar_wait_sleep(bars + B_G1DONE + 16, 0, 500);
                    flag_wait(&g_flag_part[blockIdx.x], 1, F_SLEEP);
                    asm volatile("fence.proxy.async;" ::: "memory");
                    mbar_expect_tx(bars + B_PART, 32768 + 1024);
                    bulk_load(base + OFF_X, g_part_o + blockIdx.x * 2048, 32768, bars + B_PART);
                    bulk_load(base + OFF_PART_L, g_part_l + blockIdx.x * 256, 1024, bars + B_PART);
                }
            }
        } else if (wid == 17 && leader) {
            for (int r = 0; r < 3; r++) {
                mbar_wait_sleep(bars + B_G1DONE + 8 * r, 0, 200);
                flag_signal(&g_flag_qkv[g1_tile(r, cluster)]);
            }
            for (int tl = 0; tl < A_TILES; tl++) {
                mbar_wait_sleep(bars + B_ODONE + 8 * tl, 0, tl < A_TILES - 1 ? A_SLEEP : 50);
                flag_signal(&g_flag_o[tl * 8 + (blockIdx.x & 7)]);
                if (tl == 1) asm volatile("cp.async.bulk.prefetch.L2.global [%0], %1;"
                    :: "l"(maps.pwo[blockIdx.x >> 6] + (blockIdx.x & 63) * (D_MODEL * D_MODEL / 64)), "r"(D_MODEL * D_MODEL * 2 / 64) : "memory");
            }
        } else if (wid == 18) {
            for (int tl = 0; tl < A_TILES; tl++) {
                const int head = head_of(tl), blk = head >> 5, h = head & 31;
                if (lane < 3) flag_wait(&g_flag_qkv[blk * 12 + lane * 4 + (h >> 3)], 16, spare ? 100 : F_SLEEP);
                __syncwarp();
                if (lane == 0) mbar_arrive(bars + B_READY + 8 * tl);
                float mx[3];
                #pragma unroll 1
                for (int w = 0; w < 3; w++) {
                    uint32_t m = 0;
                    #pragma unroll 4
                    for (int i = 0; i < 8; i++) {
                        uint4 v;
                        asm volatile("ld.relaxed.gpu.global.v4.u32 {%0, %1, %2, %3}, [%4];" : "=r"(v.x), "=r"(v.y), "=r"(v.z), "=r"(v.w)
                                     : "l"(g_norm + (blk * 96 + w * 32 + h) * 1024 + i * 128 + lane * 4) : "memory");
                        m = __vmaxu2(__vmaxu2(m, v.x), __vmaxu2(v.y, __vmaxu2(v.z, v.w)));
                    }
                    const float r = __uint_as_float(__reduce_max_sync(~0u, max(m << 16, m & 0xFFFF0000u)));
                    if (w == 0) mx[0] = r; else if (w == 1) mx[1] = r; else mx[2] = r;
                }
                const float q2 = mx[0], k2 = mx[1], v2 = mx[2];
                const bool ok = (q2 <= 1e18f) && (k2 <= 1e18f) && (q2 * k2 <= 6000.0f) &&
                                (v2 >= 9.1e-13f) && (v2 <= 1.1e18f);
                if (lane == 0) {
                    asm volatile("st.shared.b32 [%0], %1;" :: "r"(bars + B_MODEVAL + 4 * tl), "r"((uint32_t)ok) : "memory");
                    mbar_arrive(bars + B_MODE + 8 * tl);
                }
            }
            if (lane == 0) {
                for (int hf = 0; hf < 2 && !spare; hf++) {
                    flag_wait(&g_flag_o[(blk3 * 2 + hf) * 8 + (mt >> 1)], 16, blk3 + hf == 2 ? 100 : F_SLEEP);
                    mbar_arrive(bars + B_GFLAG + 8 * hf);
                }
                uint32_t old;
                asm volatile("atom.acq_rel.gpu.global.add.u32 %0, [%1], 1;" : "=r"(old) : "l"(&g_done) : "memory");
                if (old == gridDim.x - 1) {
                    for (int i = 0; i < 24; i++) g_flag_qkv[i] = 0;
                    for (int i = 0; i < 32; i++) g_flag_o[i] = 0;
                    for (int i = 0; i < 128; i++) g_flag_part[i] = 0;
                    g_done = 0;
                }
            }
        }
        __syncwarp();
    } else {
        reg_inc<112>();
        asm volatile("bar.sync 1, 512;" ::: "memory");
        if (wid >> 2 == 3) Turn(384).pass();
        auto g1_done = [&](int r) { __syncwarp(); if ((tid_now() & 31) == 0) mbar_arrive(bars + B_G1DONE + 8 * r); };
        auto park_addr = [&](int i) {
            return base + (i < 4 ? OFF_X + i * 8192 : i < 6 ? A_T_BYTES + (i - 4) * 8192 : OFF_X - A_T_BYTES + (i - 6) * 8192) + tid_now() * 16;
        };
        auto park = [&](int i, const uint32_t* v) {
            asm volatile("st.shared.v4.b32 [%0], {%1, %2, %3, %4};" :: "r"(park_addr(i)), "r"(v[0]), "r"(v[1]), "r"(v[2]), "r"(v[3]) : "memory");
        };
        if (!spare) {
            const int wg = wg_now();
            const uint32_t tid1 = tid_now();
            uint4* chunk = nullptr;
            uint32_t* norm = nullptr;
            bool is_q = false;
            auto aim = [&](int r) {
                const uint32_t t = tid_now();
                const int ct = g1_tile(r, cluster), hb = ct * 8 + (wg >> 1) * 4;
                chunk = reinterpret_cast<uint4*>(g_qkv) + hb * (S_LEN * 4) + mt * 512 + ((t & 0xE0) << 1) + (t & 31);
                norm = g_norm + hb * 1024 + mt * 64 + ((t & 255) >> 2);
                is_q = ct % 12 < 4;
            };
            const bool quad0 = (tid1 & 3) == 0;
            uint32_t pk[16];
            auto quad_norm = [&](const uint32_t* v) {
                const uint32_t a = hfma2_bf16(v[3], v[3], hfma2_bf16(v[2], v[2], hfma2_bf16(v[1], v[1], hfma2_bf16(v[0], v[0], 0u))));
                const uint32_t b = hfma2_bf16(v[7], v[7], hfma2_bf16(v[6], v[6], hfma2_bf16(v[5], v[5], hfma2_bf16(v[4], v[4], 0u))));
                uint32_t n = hfma2_bf16(__byte_perm(a, b, 0x5410), 0x3F803F80u, __byte_perm(a, b, 0x7632));
                n = hfma2_bf16(__shfl_xor_sync(~0u, n, 1), 0x3F803F80u, n);
                return hfma2_bf16(__shfl_xor_sync(~0u, n, 2), 0x3F803F80u, n);
            };
            auto put_norm = [&](int head, const uint32_t* v) {
                const uint32_t n = quad_norm(v);
                if (quad0) norm[head * 1024] = n;
            };
            auto put_head = [&](int head, uint32_t* v) {
                if (is_q) {
                    #pragma unroll
                    for (int i = 0; i < 8; i++) v[i] = hfma2_bf16(v[i], 0x3E833E83u, hfma2_bf16(v[i], 0xBA58BA58u, 0x80008000u));
                }
                chunk[head * (S_LEN * 4)] = make_uint4(v[0], v[1], v[2], v[3]);
                chunk[head * (S_LEN * 4) + 32] = make_uint4(v[4], v[5], v[6], v[7]);
            };
            auto reload = [&]() {
                #pragma unroll
                for (int i = 0; i < 4; i++)
                    asm volatile("ld.shared.v4.b32 {%0, %1, %2, %3}, [%4];" : "=r"(pk[4 * i]), "=r"(pk[4 * i + 1]), "=r"(pk[4 * i + 2]),
                                 "=r"(pk[4 * i + 3]) : "r"(park_addr(i)) : "memory");
            };
            #pragma unroll
            for (int i = 0; i < 16; i++) pk[i] = 0;
            #pragma unroll 1
            for (int r = 0; r < 3; r++) {
                float acc[64];
                gemm_tile<0, false>(acc, bars, maps, wg, tid1, [&](int k4, int j) {
                    const int step = r == 0 && k4 < 3 ? -1 : k4;
                    if (j == 1) { if (step == 0) put_head(2, pk); else if (step == 1) reload(); else if (step == 2) { put_norm(1, pk + 8); g1_done(r - 1); } }
                    if (j == 2) { if (step == 0) put_norm(2, pk); else if (step == 1) put_head(0, pk); }
                    if (j == 3) { if (step == 0) put_head(3, pk + 8); else if (step == 1) put_norm(0, pk); }
                    if (j == 0) { if (step == 1) put_norm(3, pk + 8); else if (step == 2) put_head(1, pk + 8); else if (step == 3) aim(r); }
                });
                uint32_t w[16];
                #pragma unroll
                for (int i = 0; i < 16; i++) {
                    const int a = 16 * (i >> 3) + 4 * (i & 3) + ((i >> 2) & 1) * 2;
                    w[i] = pack_bf16(acc[a], acc[a + 1]);
                    pk[i] = pack_bf16(acc[32 + a], acc[33 + a]);
                }
                #pragma unroll
                for (int i = 0; i < 4; i++) park(i, w + 4 * i);
                if (r == 2) {
                    const uint32_t n0 = quad_norm(w), n1 = quad_norm(w + 8), n2 = quad_norm(pk), n3 = quad_norm(pk + 8), t = tid_now();
                    norm[(t & 3) * 1024] = t & 2 ? (t & 1 ? n3 : n2) : (t & 1 ? n1 : n0);
                    mbar_wait(bars + B_GEMPTY, 1);
                    park(4, pk); park(5, pk + 4);
                    mbar_wait(bars + B_GEMPTY + 24, 1);
                    park(6, pk + 8); park(7, pk + 12);
                }
            }
        }
        auto unpark = [&](int n) {
            const uint32_t t = tid_now(), src = base + (n ? OFF_X - 2 * A_T_BYTES + n * A_T_BYTES : A_T_BYTES) + t * 16;
            uint4 v0, v1;
            asm volatile("ld.shared.v4.b32 {%0, %1, %2, %3}, [%4];" : "=r"(v0.x), "=r"(v0.y), "=r"(v0.z), "=r"(v0.w) : "r"(src) : "memory");
            asm volatile("ld.shared.v4.b32 {%0, %1, %2, %3}, [%4];" : "=r"(v1.x), "=r"(v1.y), "=r"(v1.z), "=r"(v1.w) : "r"(src + 8192) : "memory");
            uint4* dst = reinterpret_cast<uint4*>(g_qkv) + ((g1_tile(2, cluster) * 8 + ((n + 2) & 3)) * S_LEN + mt * 128) * 4;
            dst += (t >> 8) * (4 * S_LEN * 4) + ((t & 0xE0) << 1) + (t & 31);
            dst[0] = v0; dst[32] = v1;
        };

        {
            const uint32_t tid2 = tid_now();
            const bool lane0 = (tid2 & 31) == 0;
            const uint32_t qrow = ((tid2 & 0x1E0) >> 1) + (tid2 & 15), orow = ((tid2 & 0x1E0) >> 1) + ((tid2 & 31) >> 2);
            const uint32_t q_addr = base + qrow * 64 + ((((tid2 >> 4) & 1) ^ ((qrow >> 1) & 3)) << 4);
            const uint32_t bar_full = bars + B_AFULL, bar_empty = bars + B_AEMPTY;
            float sacc[32], o[20];
            uint32_t p[16], q[8];
            const bool rel = (tid2 & 127) == 0;
            uint32_t empty_peer;
            asm("mapa.shared::cluster.u32 %0, %1, %2;" : "=r"(empty_peer) : "r"(bar_empty), "r"(rank ^ 1));
            auto release = [&](uint32_t s8) {
                if (rel) {
                    mbar_arrive(bar_empty + s8);
                    asm volatile("mbarrier.arrive.shared::cluster.b64 _, [%0];" :: "r"(empty_peer + s8) : "memory");
                }
            };
            __nv_bfloat16* const o_ptr = g_o + ((blockIdx.x & 7) * 256 + orow) * D_MODEL + (blockIdx.x >> 3) * D_HEAD + 8 * (tid2 & 3);
            float inv0 = 0.f, inv1 = 0.f;
            auto store_tile = [&](int tl) { store_o(o, inv0, inv1, o_ptr + (tl >> 1) * (S_LEN * D_MODEL) + (tl & 1) * (16 * D_HEAD)); };
            auto close_tile = [&](int tl, bool fast) {
                if (fast && tl == tl_give) {
                    mbar_wait(bars + B_PART, 0);
                    const uint32_t t = tid_now(), l_addr = base + OFF_PART_L + ((t & 0x1E0) << 1) + (t & 28);
                    #pragma unroll
                    for (int i = 0; i < 4; i++) {
                        float4 v;
                        asm volatile("ld.shared.v4.f32 {%0, %1, %2, %3}, [%4];" : "=f"(v.x), "=f"(v.y), "=f"(v.z), "=f"(v.w)
                                     : "r"(base + OFF_X + i * 8192 + t * 16) : "memory");
                        o[4 * i] += v.x; o[4 * i + 1] += v.y; o[4 * i + 2] += v.z; o[4 * i + 3] += v.w;
                    }
                    o[16] += __uint_as_float(lds32(l_addr));
                    o[18] += __uint_as_float(lds32(l_addr + 32));
                }
                inv_sums(o, inv0, inv1);
            };
            auto signal_tile = [&](int tl) { __syncwarp(); if (lane0) mbar_arrive(bars + B_ODONE + 8 * tl); };
            auto last_stage = [&](int tl) -> const Stage& { return maps.stage[tl * A_NST + A_NST - 1 - (tl == tl_give)]; };
            auto last_v = [&](int tl) { return last_stage(tl).dv + (uint64_t)(3 * 256) * V_STEP; };
            auto flush_pending = [&](int tl) {
                fence_regs(p); fence_regs(o);
                wg_fence();
                mma_pv(o, p, last_v(tl), 1);
                wg_commit();
                wg_wait<0>();
                fence_regs(o);
                release(last_stage(tl).slot8);
                close_tile(tl, true);
                store_tile(tl);
                signal_tile(tl);
            };
            uint32_t m0, m1;
            asm volatile("ld.shared.v2.b32 {%0, %1}, [%2];" : "=r"(m0), "=r"(m1) : "r"(bars + B_CONST + (tid2 & 1) * 8) : "memory");
            const uint32_t nv = lds32(bars + B_CONST);
            const Turn turn(tid2);
            #pragma unroll
            for (int i = 0; i < 16; i++) p[i] = 0;
            #pragma unroll
            for (int i = 0; i < 20; i++) o[i] = 0.f;
            if (spare) {
                float4* dst = g_part_o + (blockIdx.x - 128) * (32 * 2048) + tid2;
                float* dl = g_part_l + (blockIdx.x - 128) * (32 * 256) + orow;
                auto put_partial = [&](int n) {
                    #pragma unroll
                    for (int i = 0; i < 4; i++) dst[i * 512] = make_float4(o[4 * i], o[4 * i + 1], o[4 * i + 2], o[4 * i + 3]);
                    if ((tid2 & 3) == 0) { dl[0] = o[16]; dl[8] = o[18]; }
                    dst += 2048; dl += 256;
                    __syncwarp();
                    if (lane0) mbar_arrive(base + OFF_X + 8 * n);
                };
                mbar_wait(bars + B_QFULL, 0);
                load_q(q, q_addr);
                if (lane0) mbar_arrive(bars + B_QEMPTY);
                uint64_t dv_prev = 0;
                #pragma unroll 1
                for (int n = 0; n < 32; n++) {
                    const uint64_t dk = maps.stage[n >> 3].dk, dv = maps.stage[n >> 3].dv;
                    mbar_wait_hot(bar_full + (n & 24), 0);
                    #pragma unroll
                    for (int u = 0; u < 4; u++) {
                        fence_regs(p); fence_regs(o); fence_regs(q);
                        turn.take();
                        if (u == 0) {
                            if (n != 0) { wg_fence(); mma_pv(o, p, dv_prev, 1); }
                            wg_fence();
                        } else {
                            wg_fence();
                            mma_pv(o, p, dv + (uint64_t)((u - 1) * 256) * V_STEP, u > 1);
                        }
                        mma_qk(sacc, q, dk + u * 256);
                        wg_commit();
                        turn.pass();
                        const int nq = min(n + 1, 31);
                        if (u == 3) mbar_wait_hot(bars + B_QFULL + 8 * (nq & 1), (nq >> 1) & 1);
                        wg_wait<0>();
                        fence_regs(sacc); fence_regs(o); fence_regs(p); fence_regs(q);
                        if (u == 3) {
                            load_q(q, q_addr + (nq & 1) * A_T_BYTES);
                            if (lane0) mbar_arrive(bars + B_QEMPTY + 8 * (nq & 1));
                        }
                        if (u == 0) exp_fast<0>(sacc, p, m0, m1, nv); else if (u == 1) exp_fast<1>(sacc, p, m0, m1, nv);
                            else if (u == 2) exp_fast<2>(sacc, p, m0, m1, nv); else exp_fast<3>(sacc, p, m0, m1, nv);
                        if (u == 0 && n != 0) put_partial(n - 1);
                    }
                    dv_prev = dv + (uint64_t)(3 * 256) * V_STEP;
                }
                fence_regs(p); fence_regs(o);
                wg_fence();
                mma_pv(o, p, dv_prev, 1);
                wg_commit();
                wg_wait<0>();
                fence_regs(o);
                put_partial(31);
            }
            bool pending = false;
            for (int tl = 0; tl < A_TILES && !spare; tl++) {
                mbar_wait_hot(bars + B_QFULL + 8 * (tl & 1), (tl >> 1) & 1);
                const uint32_t fast = lds32(bars + B_MODEVAL + 4 * tl);
                const uint32_t c0 = tl * A_NST;
                load_q(q, q_addr + (tl & 1) * A_T_BYTES);
                fence_regs(q);
                if (lane0) mbar_arrive(bars + B_QEMPTY + 8 * (tl & 1));
                if (__shfl_sync(~0u, fast, 0)) {
                    const uint64_t dv_first = last_v(max(tl - 1, 0));
                    uint32_t sp8 = pending ? last_stage(tl - 1).slot8 : B_DUMMY - B_AEMPTY;
                    uint32_t s8 = maps.stage[c0].slot8;
                    mbar_wait_hot(bar_full + s8, maps.stage[c0].parity);
                    uint32_t next = (c0 + 1) * sizeof(Stage);
                    auto stage = [&](auto first, int st) {
                        constexpr bool FIRST = decltype(first)::value;
                        const Stage& cur = *reinterpret_cast<const Stage*>(reinterpret_cast<const char*>(maps.stage) + next - sizeof(Stage));
                        const uint64_t dk = cur.dk, dv = cur.dv, dv_prev = FIRST && st == 0 ? dv_first : cur.dv_prev;
                        uint32_t s8_n = 0;
                        #pragma unroll
                        for (int u = 0; u < 4; u++) {
                            fence_regs(p); fence_regs(o);
                            turn.take();
                            if (FIRST && u == 0) {
                                if (pending || st != 0) { wg_fence(); mma_pv(o, p, dv_prev, 1); }
                                wg_fence();
                            } else {
                                wg_fence();
                                mma_pv(o, p, u == 0 ? dv_prev : dv + (uint64_t)((u - 1) * 256) * V_STEP, FIRST && u == 1 ? st != 0 : 1);
                            }
                            mma_qk(sacc, q, dk + u * 256);
                            wg_commit();
                            turn.pass();
                            if (FIRST && u == 2 && tl == 0) {
                                unpark(st);
                                if (st & 1) g1_done(st == 1 ? 3 : 2);
                            }
                            if (u == 3) {
                                const Stage& sg = *reinterpret_cast<const Stage*>(reinterpret_cast<const char*>(maps.stage) + next);
                                s8_n = sg.slot8;
                                mbar_wait_hot(bar_full + s8_n, sg.parity);
                            }
                            wg_wait<0>();
                            fence_regs(sacc); fence_regs(o); fence_regs(p);
                            if (u == 0) {
                                release(sp8);
                                if (FIRST && pending) close_tile(tl - 1, true);
                            }
                            if (u == 0) exp_fast<0>(sacc, p, m0, m1, nv); else if (u == 1) exp_fast<1>(sacc, p, m0, m1, nv);
                            else if (u == 2) exp_fast<2>(sacc, p, m0, m1, nv); else exp_fast<3>(sacc, p, m0, m1, nv);
                            if (FIRST && u == 0 && pending) { store_tile(tl - 1); signal_tile(tl - 1); }
                        }
                        sp8 = s8; s8 = s8_n; next += sizeof(Stage);
                    };
                    const int n_first = tl == 0 ? 4 : 1;
                    int st = 0;
                    #pragma unroll 1
                    do { stage(Const<1>{}, st); } while (++st < n_first);
                    const uint32_t end = (c0 + A_NST + 1 - (tl == tl_give)) * sizeof(Stage);
                    #pragma unroll 1
                    do { stage(Const<0>{}, 1); } while (next != end);
                    if (tl == tl_give) release(s8);
                    pending = true;
                } else {
                    if (pending) { flush_pending(tl - 1); pending = false; }
                    if (tl == 0) { for (int i = 0; i < 4; i++) unpark(i); g1_done(3); g1_done(2); }
                    float m0 = -INFINITY, m1 = -INFINITY;
                    #pragma unroll
                    for (int i = 0; i < 20; i++) o[i] = 0.f;
                    for (int st = 0; st < A_NST; st++) {
                        const Stage& sg = maps.stage[c0 + st];
                        mbar_wait(bar_full + sg.slot8, sg.parity);
                        const uint64_t dk = sg.dk, dv = sg.dv;
                        #pragma unroll 1
                        for (int u = 0; u < 4; u++) {
                            wg_fence();
                            mma_qk(sacc, q, dk + u * 256);
                            wg_commit();
                            wg_wait<0>();
                            fence_regs(sacc);
                            float x0 = m0, x1 = m1;
                            #pragma unroll
                            for (int i = 0; i < 8; i++) {
                                x0 = fmaxf(x0, fmaxf(sacc[4 * i], sacc[4 * i + 1]));
                                x1 = fmaxf(x1, fmaxf(sacc[4 * i + 2], sacc[4 * i + 3]));
                            }
                            x0 = fmaxf(x0, __shfl_xor_sync(~0u, x0, 1)); x1 = fmaxf(x1, __shfl_xor_sync(~0u, x1, 1));
                            x0 = fmaxf(x0, __shfl_xor_sync(~0u, x0, 2)); x1 = fmaxf(x1, __shfl_xor_sync(~0u, x1, 2));
                            const float a0 = ex2(m0 - x0), a1 = ex2(m1 - x1);
                            m0 = x0; m1 = x1;
                            #pragma unroll
                            for (int i = 0; i < 5; i++) { o[4 * i] *= a0; o[4 * i + 1] *= a0; o[4 * i + 2] *= a1; o[4 * i + 3] *= a1; }
                            #pragma unroll
                            for (int i = 0; i < 8; i++) {
                                p[2 * i] = pack_bf16(ex2(sacc[4 * i] - m0), ex2(sacc[4 * i + 1] - m0));
                                p[2 * i + 1] = pack_bf16(ex2(sacc[4 * i + 2] - m1), ex2(sacc[4 * i + 3] - m1));
                            }
                            fence_regs(p); fence_regs(o);
                            wg_fence();
                            mma_pv(o, p, dv + (uint64_t)(u * 256) * V_STEP, 1);
                            wg_commit();
                            wg_wait<0>();
                            fence_regs(o); fence_regs(p);
                        }
                        release(sg.slot8);
                    }
                    close_tile(tl, false);
                    store_tile(tl);
                    signal_tile(tl);
                }
            }
            if (pending) flush_pending(A_TILES - 1);
        }

        if (!spare) {
            float acc[64];
            const int wg = wg_now();
            gemm_tile<2, true>(acc, bars, maps, wg, tid_now(), [](int, int) {});
            const uint32_t tid3 = tid_now();
            const int warp = (tid3 >> 5) & 3, lane = tid3 & 31;
            const uint32_t stg = base + (wg >= 2 ? 2 * G_STAGE_BYTES : OFF_X) + (wg & 1) * 16384 + warp * 4096;
            const int rr = (lane & 7) + ((lane >> 3) & 1) * 8;
            #pragma unroll
            for (int jp = 0; jp < 8; jp++) {
                const int i = 8 * jp;
                const uint32_t r0 = pack_bf16(acc[i], acc[i + 1]), r1 = pack_bf16(acc[i + 2], acc[i + 3]);
                const uint32_t r2 = pack_bf16(acc[i + 4], acc[i + 5]), r3 = pack_bf16(acc[i + 6], acc[i + 7]);
                const uint32_t addr = stg + rr * 256 + (((2 * jp + (lane >> 4)) ^ (rr & 7)) << 4);
                asm volatile("stmatrix.sync.aligned.m8n8.x4.shared.b16 [%0], {%1, %2, %3, %4};"
                             :: "r"(addr), "r"(r0), "r"(r1), "r"(r2), "r"(r3) : "memory");
            }
            __syncwarp();
            uint4* dst = reinterpret_cast<uint4*>(out + (size_t)(mt * 128 + (wg & 1) * 64 + warp * 16 + (lane >> 4)) * (2 * D_MODEL) +
                                                  blk3 * D_MODEL + nt3 * 256 + (wg >> 1) * 128) + (lane & 15);
            #pragma unroll
            for (int i = 0; i < 8; i++) {
                const int row = 2 * i + (lane >> 4);
                uint4 v;
                asm volatile("ld.shared.v4.b32 {%0, %1, %2, %3}, [%4];" : "=r"(v.x), "=r"(v.y), "=r"(v.z), "=r"(v.w)
                             : "r"(stg + row * 256 + (((lane & 15) ^ (row & 7)) << 4)) : "memory");
                dst[i * (2 * 2 * D_MODEL / 8)] = v;
            }
        }
        if (wg_now() == 0) Turn(0).take();
    }
}

typedef CUresult (*EncodeFn)(CUtensorMap*, CUtensorMapDataType, cuuint32_t, void*, const cuuint64_t*, const cuuint64_t*,
                             const cuuint32_t*, const cuuint32_t*, CUtensorMapInterleave, CUtensorMapSwizzle,
                             CUtensorMapL2promotion, CUtensorMapFloatOOBfill);

void encode(EncodeFn fn, CUtensorMap* m, const void* ptr, int rank, const cuuint64_t* dims, const cuuint64_t* strides,
            const cuuint32_t* box, CUtensorMapSwizzle sw) {
    const cuuint32_t es[3] = {1, 1, 1};
    fn(m, CU_TENSOR_MAP_DATA_TYPE_BFLOAT16, rank, const_cast<void*>(ptr), dims, strides, box, es,
       CU_TENSOR_MAP_INTERLEAVE_NONE, sw, CU_TENSOR_MAP_L2_PROMOTION_L2_128B, CU_TENSOR_MAP_FLOAT_OOB_FILL_NONE);
}
void map_rows(EncodeFn fn, CUtensorMap* m, const void* p, int rows, int cols, int box_r, int box_c, CUtensorMapSwizzle sw) {
    const cuuint64_t dims[2] = {(cuuint64_t)cols, (cuuint64_t)rows}, st[1] = {(cuuint64_t)cols * 2};
    const cuuint32_t box[2] = {(cuuint32_t)box_c, (cuuint32_t)box_r};
    encode(fn, m, p, 2, dims, st, box, sw);
}
void map_weight(EncodeFn fn, CUtensorMap* m, const void* p, int K, int N) {
    const cuuint64_t dims[3] = {64, (cuuint64_t)K, (cuuint64_t)N / 64}, st[2] = {(cuuint64_t)N * 2, 128};
    const cuuint32_t box[3] = {64, 64, 2};
    encode(fn, m, p, 3, dims, st, box, CU_TENSOR_MAP_SWIZZLE_128B);
}

void launch_impl(void* const* d_in, void* d_out) {
    void* fnp = nullptr;
    cudaDriverEntryPointQueryResult qr;
    cudaGetDriverEntryPoint("cuTensorMapEncodeTiled", &fnp, cudaEnableDefault, &qr);
    EncodeFn fn = (EncodeFn)fnp;
    void *qkv, *o;
    cudaGetSymbolAddress(&qkv, g_qkv);
    cudaGetSymbolAddress(&o, g_o);

    Maps m;
    for (int b = 0; b < 2; b++) {
        map_rows(fn, &m.x[b], d_in[3 * b], S_LEN, D_MODEL, 128, 64, CU_TENSOR_MAP_SWIZZLE_128B);
        map_weight(fn, &m.wqkv[b], d_in[3 * b + 1], D_MODEL, 3 * D_MODEL);
        map_weight(fn, &m.wo[b], d_in[3 * b + 2], D_MODEL, D_MODEL);
        m.pwo[b] = (const __nv_bfloat16*)d_in[3 * b + 2];
    }
    map_rows(fn, &m.o, o, 2 * S_LEN, D_MODEL, 128, 64, CU_TENSOR_MAP_SWIZZLE_128B);
    map_rows(fn, &m.qkv, qkv, 2 * 3 * N_HEAD * S_LEN, D_HEAD, 256, D_HEAD, CU_TENSOR_MAP_SWIZZLE_64B);

    m.zero = 0;
    m.da = mk_desc(SMEM_ORG, 16, 1024, 1);
    m.db = mk_desc(SMEM_ORG + G_A_BYTES, 8192, 1024, 1);
    for (int c = 0; c < A_TILES * A_NST; c++) {
        const int s = c % A_STAGES, sp = (c + A_STAGES - 1) % A_STAGES;
        const int off_k = OFF_KV + s * A_STAGE_BYTES, off_v = off_k + A_T_BYTES, off_p = OFF_KV + (sp + 1) * A_STAGE_BYTES - 4096;
        m.stage[c].dk = mk_desc(SMEM_ORG + off_k, 16, 512, 2);
        m.stage[c].dv = mk_desc(SMEM_ORG + off_v, OFF_ONES - off_v, 512, 2);
        m.stage[c].dv_prev = mk_desc(SMEM_ORG + off_p, OFF_ONES - off_p, 512, 2);
        m.stage[c].slot8 = 8 * s; m.stage[c].parity = (c / A_STAGES) & 1;
    }
    m.stage[A_TILES * A_NST] = m.stage[A_TILES * A_NST - 1];

    cudaFuncSetAttribute(mha2_kernel, cudaFuncAttributeMaxDynamicSharedMemorySize, SMEM_BYTES);
    cudaLaunchConfig_t cfg = {};
    cfg.gridDim = dim3(132); cfg.blockDim = dim3(640); cfg.dynamicSmemBytes = SMEM_BYTES;
    cudaLaunchAttribute at;
    at.id = cudaLaunchAttributeClusterDimension; at.val.clusterDim.x = 2; at.val.clusterDim.y = 1; at.val.clusterDim.z = 1;
    cfg.attrs = &at; cfg.numAttrs = 1;
    int fit = 0;
    cudaOccupancyMaxActiveClusters(&fit, mha2_kernel, &cfg);
    mha2_kernel<<<fit >= 66 ? 132 : 128, 640, SMEM_BYTES, cudaStreamPerThread>>>(m, (__nv_bfloat16*)d_out);
}

}

extern "C" void kernel_launch(void* const* d_in, const int* in_sizes, int n_in, void* d_out, int out_size) {
    (void)in_sizes; (void)n_in; (void)out_size;
    launch_impl(d_in, d_out);
}
```
